```python
import torch

def _softmax(x, axis=-1):
    return torch.softmax(x, dim=axis)
def _gelu(x):
    return torch.nn.functional.gelu(x, approximate="tanh")
def _silu(x):
    return torch.nn.functional.silu(x)
def _sigmoid(x):
    return torch.sigmoid(x)
def _layernorm(x, axis=-1, eps=1e-5):
    m = x.mean(dim=axis, keepdim=True)
    v = x.var(dim=axis, keepdim=True, unbiased=False)
    return (x - m) / torch.sqrt(v + eps)
def _scatter_add(tgt, idx, src, axis=0):
    return tgt.clone().index_add_(axis, idx, src)
def _segment_sum(src, seg, n):
    out = torch.zeros((n,) + src.shape[1:], dtype=src.dtype)
    return out.index_add_(0, seg, src)
def _pad(x, pw):
    flat = tuple(v for pair in reversed(pw) for v in pair)
    return torch.nn.functional.pad(x, flat)

kernel_name = 'standalone__edge_featured_mpnn_egc__graph'

def setup_inputs():

    _w = (lambda a: (lambda t: t.to(torch.bfloat16) if t.is_floating_point() else t)(torch.as_tensor(a)))
    N, deg, D, De = 50000, 16, 64, max(4, 1)
    E = N * deg
    return {
        "x": _w((lambda *s: torch.randn(*s, dtype=torch.bfloat16) * 0.2)(N, D)),
        "e_attr": _w((lambda *s: torch.randn(*s, dtype=torch.bfloat16) * 0.2)(E, De)),
        "src": _w((lambda lo, hi, *s: torch.randint(lo, hi, s))(0, N, E).to(torch.int64)),
        "dst": _w((lambda lo, hi, *s: torch.randint(lo, hi, s))(0, N, E).to(torch.int64)),
        "u_w": _w((lambda *s: torch.randn(*s, dtype=torch.bfloat16) * 0.05)(D, D)),
        "v_w": _w((lambda *s: torch.randn(*s, dtype=torch.bfloat16) * 0.05)(D, D)),
        "g_w": _w((lambda *s: torch.randn(*s, dtype=torch.bfloat16) * 0.2)(2 * D + De, D)),
    }

def reference(x, e_attr, src, dst, u_w, v_w, g_w):
    N, D = x.shape
    g_in = torch.concatenate([x[dst], x[src], e_attr], axis=-1)
    eta = _sigmoid(g_in @ g_w)
    hv = x @ v_w
    msg = eta * hv[src]
    agg = _segment_sum(msg, dst, N)
    return _silu(x @ u_w + agg)
```

```cpp
#include <cuda_runtime.h>
#include <cuda.h>
#include <cuda_bf16.h>
#include <stdint.h>

namespace {

constexpr int kN = 50000;
constexpr int kE = 800000;
constexpr int NCTA = 132;
constexpr int NB = 380;
constexpr int NTHR = 512;
constexpr int NQUAD = kE / 4;
constexpr int CQ = 1516;
constexpr int OUTC = 2112;
constexpr int CAPC = 2304;
constexpr int WIN = 4;
constexpr int XE = 4;
constexpr int EE = 3;
constexpr int UNP = 2;
constexpr int DYN = 24;
constexpr int PACE = 2;
constexpr int NPRE = 5;

constexpr int SM_XS = 0;
constexpr int SM_KS = 49152;
constexpr int SM_AUX = SM_KS + CAPC * 16;
constexpr int SM_DST = SM_KS, SM_SRC = SM_KS + 24576;
constexpr int SM_XA = SM_AUX + 18432;
constexpr int SM_SK = SM_XA + 194 * 256;
constexpr int SM_SS = SM_SK + (3 * CAPC + 64) * 4;
constexpr int SM_OH = SM_SK + OUTC * 12;
constexpr int SM_TBL = SM_SK + (3 * CAPC + 64) * 8;
constexpr int SM_CNT1 = SM_TBL + 3072;
constexpr int SM_OFF1 = SM_CNT1;
constexpr int SM_CNT2 = SM_CNT1 + 640;
constexpr int SM_PST = SM_CNT2 + 1024;
constexpr int SM_VAR = SM_PST + 1024;
constexpr int SM_BAR = SM_VAR + 80;
constexpr int SM_LBAR = SM_BAR + 216;
constexpr int LB_DST = SM_LBAR, LB_SRC = SM_LBAR + 32, LB_OWN = SM_LBAR + 64, LB_W = SM_LBAR + 112, LB_TAG = SM_LBAR + 120;
constexpr int SM_U = SM_LBAR + 136;
constexpr int SM_END = SM_U + 8192;
constexpr int SMEM_BYTES = SM_END;
static_assert(SMEM_BYTES <= 232448 && SM_XA % 1024 == 0 && SM_XA >= NB * 256 && SM_AUX >= 73728 && SM_XA >= SM_KS + 49152 && SM_U % 16 == 0, "smem");
static_assert(OUTC * 3 >= CQ * 4 + 2 * NCTA && CQ * NCTA >= NQUAD && CAPC == 6 * 384, "capacities");
static_assert(XE >= 4 && XE < 6, "borrowed pairs need the neighbour's xa at the start");
__host__ __device__ constexpr int xs_off(int stage) { return SM_XS + ((stage + 2) % 3) * 24576; }

constexpr int BAR_CONS = 1, BAR_R = 2, BAR_S = 3, BAR_KEYS = 4, BAR_IN = 5, BAR_B = 6, BAR_C = 7, BAR_D = 8, BAR_G = 9;

constexpr int KOFF = 40, KSTR = OUTC + KOFF;
__device__ __align__(128) uint4 g_keys[NCTA * KSTR];
__device__ uint32_t g_epoch;
#define entry_ptr(c, b) ((uint32_t*)(keys_g + (c) * KSTR) + (b))

__device__ __forceinline__ void wg_fence() { asm volatile("wgmma.fence.sync.aligned;" ::: "memory"); }
__device__ __forceinline__ void wg_commit() { asm volatile("wgmma.commit_group.sync.aligned;" ::: "memory"); }
template <int n> __device__ __forceinline__ void wg_wait() { asm volatile("wgmma.wait_group.sync.aligned %0;" ::"n"(n) : "memory"); }
__device__ __forceinline__ void fence_async() { asm volatile("fence.proxy.async.shared::cta;" ::: "memory"); }
__device__ __forceinline__ void bar_sync(int id, int n) { asm volatile("bar.sync %0, %1;" ::"r"(id), "r"(n) : "memory"); }
__device__ __forceinline__ void bar_arrive(int id, int n) { asm volatile("bar.arrive %0, %1;" ::"r"(id), "r"(n) : "memory"); }
__device__ __forceinline__ void cp16(uint32_t s, const void* g) {
    asm volatile("cp.async.cg.shared.global [%0], [%1], 16;" ::"r"(s), "l"(g) : "memory");
}
__device__ __forceinline__ float tanh_ap(float x) { float y; asm("tanh.approx.f32 %0, %1;" : "=f"(y) : "f"(x)); return y; }
__device__ __forceinline__ float tanh_v(float x) { float y; asm volatile("tanh.approx.f32 %0, %1;" : "=f"(y) : "f"(x)); return y; }
__device__ __forceinline__ uint32_t pack_v(float lo, float hi) { uint32_t y; asm volatile("cvt.rn.bf16x2.f32 %0, %1, %2;" : "=r"(y) : "f"(hi), "f"(lo)); return y; }
__device__ __forceinline__ uint32_t pack_bf2(float lo, float hi) { uint32_t y; asm("cvt.rn.bf16x2.f32 %0, %1, %2;" : "=r"(y) : "f"(hi), "f"(lo)); return y; }
__device__ __forceinline__ uint32_t lds32(uint32_t a) { uint32_t v; asm volatile("ld.shared.u32 %0, [%1];" : "=r"(v) : "r"(a) : "memory"); return v; }
__device__ __forceinline__ uint2 lds64(uint32_t a) { uint2 v; asm volatile("ld.shared.v2.u32 {%0,%1}, [%2];" : "=r"(v.x), "=r"(v.y) : "r"(a) : "memory"); return v; }
__device__ __forceinline__ uint4 lds128(uint32_t a) { uint4 v; asm volatile("ld.shared.v4.u32 {%0,%1,%2,%3}, [%4];" : "=r"(v.x), "=r"(v.y), "=r"(v.z), "=r"(v.w) : "r"(a) : "memory"); return v; }
__device__ __forceinline__ void sts32(uint32_t a, uint32_t v) { asm volatile("st.shared.u32 [%0], %1;" ::"r"(a), "r"(v) : "memory"); }
__device__ __forceinline__ void sts64(uint32_t a, uint32_t x, uint32_t y) { asm volatile("st.shared.v2.u32 [%0], {%1,%2};" ::"r"(a), "r"(x), "r"(y) : "memory"); }
__device__ __forceinline__ void sts128(uint32_t a, uint4 v) { asm volatile("st.shared.v4.u32 [%0], {%1,%2,%3,%4};" ::"r"(a), "r"(v.x), "r"(v.y), "r"(v.z), "r"(v.w) : "memory"); }
__device__ __forceinline__ uint32_t atoms_add(uint32_t a, uint32_t v) { uint32_t r; asm volatile("atom.shared.add.u32 %0, [%1], %2;" : "=r"(r) : "r"(a), "r"(v) : "memory"); return r; }
__device__ __forceinline__ void put_record(uint32_t a, uint32_t key, uint32_t row) {
    asm volatile("st.shared.u32 [%0], %1;\nst.shared.u32 [%0+%3], %2;" ::"r"(a), "r"(key), "r"(row), "n"(SM_SS - SM_SK) : "memory");
}
__device__ __forceinline__ uint32_t ld_relaxed(const uint32_t* p) { uint32_t v; asm volatile("ld.relaxed.gpu.global.u32 %0, [%1];" : "=r"(v) : "l"(p) : "memory"); return v; }
__device__ __forceinline__ void mbar_init(uint32_t a, uint32_t n) { asm volatile("mbarrier.init.shared::cta.b64 [%0], %1;" ::"r"(a), "r"(n) : "memory"); }
__device__ __forceinline__ void mbar_arrive(uint32_t a) { asm volatile("mbarrier.arrive.shared::cta.b64 _, [%0];" ::"r"(a) : "memory"); }
__device__ __forceinline__ void mbar_cp_arrive(uint32_t a) { asm volatile("cp.async.mbarrier.arrive.noinc.shared::cta.b64 [%0];" ::"r"(a) : "memory"); }
__device__ __forceinline__ void mbar_wait(uint32_t a, uint32_t parity) {
    asm volatile("{\n.reg .pred p;\n.reg .u32 c;\n"
                 "mbarrier.try_wait.parity.shared::cta.b64 p, [%0], %1;\n@p bra WAIT_DONE;\nmov.u32 c, 0;\n"
                 "WAIT_LOOP:\nmbarrier.try_wait.parity.shared::cta.b64 p, [%0], %1;\n@p bra WAIT_DONE;\n"
                 "add.u32 c, c, 1;\nsetp.lt.u32 p, c, 0x400000;\n@p bra WAIT_LOOP;\ntrap;\nWAIT_DONE:\n}" ::"r"(a), "r"(parity) : "memory");
}
__device__ __forceinline__ void sched_fence() { asm volatile("pmevent 0;" ::: "memory"); }
__device__ __forceinline__ uint32_t lds16(uint32_t a) { uint32_t v; asm volatile("ld.shared.u16 %0, [%1];" : "=r"(v) : "r"(a) : "memory"); return v; }
__device__ __forceinline__ uint32_t opaque(uint32_t v) { return __shfl_sync(~0u, v, threadIdx.x & 31); }
__device__ __forceinline__ void mbar_arrive_if(uint32_t a, bool pred) {
    asm volatile("{\n.reg .pred p;\nsetp.ne.u32 p, %1, 0;\n@p mbarrier.arrive.shared::cta.b64 _, [%0];\n}" ::"r"(a), "r"((uint32_t)pred) : "memory");
}
__device__ __forceinline__ bool elect_one() {
    uint32_t r;
    asm volatile("{\n.reg .pred p;\nelect.sync _|p, 0xffffffff;\nselp.u32 %0, 1, 0, p;\n}" : "=r"(r));
    return r != 0;
}
template <int V> struct IC { static constexpr int value = V; };
__device__ __forceinline__ int lane_id() { int v; asm volatile("mov.u32 %0, %%laneid;" : "=r"(v)); return v; }
__device__ __forceinline__ void cp16p(uint32_t s, const void* g, bool pred) {
    asm volatile("{\n.reg .pred p;\nsetp.ne.u32 p, %2, 0;\n@p cp.async.cg.shared.global [%0], [%1], 16;\n}" ::"r"(s), "l"(g), "r"((uint32_t)pred) : "memory");
}
__device__ __forceinline__ uint32_t ldg_cg(const void* p) { uint32_t v; asm volatile("ld.global.cg.u32 %0, [%1];" : "=r"(v) : "l"(p) : "memory"); return v; }

__device__ __forceinline__ uint64_t mkdesc(uint32_t addr, uint32_t lbo, uint32_t sbo, uint32_t sw) {
    const uint32_t z = threadIdx.x >> 20;
    const uint32_t lo = __shfl_sync(~0u, (((addr & 0x3FFFF) >> 4) | ((lbo >> 4) << 16)) + z, 0);
    const uint32_t hi = __shfl_sync(~0u, ((sbo >> 4) | (sw << 30)) + lane_id() / 32, 0);
    return ((uint64_t)hi << 32) | lo;
}
template <int SCALE_D>
__device__ __forceinline__ void wg_n64(float (&d)[32], uint32_t a0, uint32_t a1, uint32_t a2, uint32_t a3, uint64_t desc) {
    asm volatile("{\n.reg .pred p;\nsetp.ne.b32 p, %37, 0;\n"
                 "wgmma.mma_async.sync.aligned.m64n64k16.f32.bf16.bf16 "
                 "{%0,%1,%2,%3,%4,%5,%6,%7,%8,%9,%10,%11,%12,%13,%14,%15,%16,%17,%18,%19,%20,%21,%22,%23,%24,%25,%26,%27,%28,%29,%30,%31}, "
                 "{%32,%33,%34,%35}, %36, p, 1, 1, 0;\n}\n"
                 : "+f"(d[0]), "+f"(d[1]), "+f"(d[2]), "+f"(d[3]), "+f"(d[4]), "+f"(d[5]), "+f"(d[6]), "+f"(d[7]),
                   "+f"(d[8]), "+f"(d[9]), "+f"(d[10]), "+f"(d[11]), "+f"(d[12]), "+f"(d[13]), "+f"(d[14]), "+f"(d[15]),
                   "+f"(d[16]), "+f"(d[17]), "+f"(d[18]), "+f"(d[19]), "+f"(d[20]), "+f"(d[21]), "+f"(d[22]), "+f"(d[23]),
                   "+f"(d[24]), "+f"(d[25]), "+f"(d[26]), "+f"(d[27]), "+f"(d[28]), "+f"(d[29]), "+f"(d[30]), "+f"(d[31])
                 : "r"(a0), "r"(a1), "r"(a2), "r"(a3), "l"(desc), "n"(SCALE_D));
}
template <int ACC>
__device__ __forceinline__ void wg_k64(float (&d)[32], const uint32_t (&w)[16], uint64_t desc) {
    wg_n64<ACC>(d, w[0], w[1], w[2], w[3], desc);
    wg_n64<1>(d, w[4], w[5], w[6], w[7], desc + 2);
    wg_n64<1>(d, w[8], w[9], w[10], w[11], desc + 4);
    wg_n64<1>(d, w[12], w[13], w[14], w[15], desc + 6);
}
__device__ __forceinline__ void wg_n8t(float (&d)[4], uint32_t a0, uint32_t a1, uint32_t a2, uint32_t a3, uint64_t desc) {
    asm volatile("{\n.reg .pred p;\nsetp.ne.b32 p, 1, 0;\n"
                 "wgmma.mma_async.sync.aligned.m64n8k16.f32.bf16.bf16 {%0,%1,%2,%3}, {%4,%5,%6,%7}, %8, p, 1, 1, 1;\n}\n"
                 : "+f"(d[0]), "+f"(d[1]), "+f"(d[2]), "+f"(d[3])
                 : "r"(a0), "r"(a1), "r"(a2), "r"(a3), "l"(desc));
}
__device__ __forceinline__ void wg_seg(float (&d)[4], const uint32_t (&m)[16], uint64_t desc) {
#pragma unroll
    for (int k = 0; k < 4; k++) wg_n8t(d, m[4 * k], m[4 * k + 1], m[4 * k + 2], m[4 * k + 3], desc + 16 * k);
}
template <int NR> __device__ __forceinline__ void fence_regs(float (&d)[NR]) {
#pragma unroll
    for (int i = 0; i < NR; i++) asm volatile("" : "+f"(d[i])::"memory");
}

__device__ __forceinline__ uint32_t scale_bf2(uint32_t v, uint32_t s) {
    uint32_t r;
    asm("fma.rn.bf16x2 %0, %1, %2, %3;" : "=r"(r) : "r"(v), "r"(s), "r"(0x80008000u));
    return r;
}
__device__ __forceinline__ void cvt_wfrag(uint32_t (&a)[16], uint32_t s) {
#pragma unroll
    for (int i = 0; i < 8; i++) {
        const uint32_t r0 = a[2 * i], r1 = a[2 * i + 1];
        a[2 * i] = scale_bf2(__byte_perm(r0, r1, 0x5410), s);
        a[2 * i + 1] = scale_bf2(__byte_perm(r0, r1, 0x7632), s);
    }
}

__device__ __forceinline__ float bf_lo(uint32_t v) { return __uint_as_float(v << 16); }
__device__ __forceinline__ float bf_hi(uint32_t v) { return __uint_as_float(v & 0xFFFF0000u); }

__device__ __noinline__ void slow_path(char* smem, const uint4* keys_g, const __nv_bfloat16* x, const __nv_bfloat16* e_attr,
                                       const __nv_bfloat16* u_w, const __nv_bfloat16* v_w, const __nv_bfloat16* g_w,
                                       __nv_bfloat16* out) {
    const int tid = threadIdx.x, warp = tid >> 5, lane = tid & 31;
    const int node0 = blockIdx.x * NB, nnodes = min(NB, kN - node0);
    const uint32_t rtag = *(const uint32_t*)(smem + SM_VAR + 52);
    float* agg = (float*)smem;
    for (int i = tid; i < NB * 64; i += 384) agg[i] = 0.f;
    bar_sync(BAR_CONS, 384);
    const int f = 2 * lane;
    for (int c = 0; c < NCTA; c++) {
        const uint32_t en = ldg_cg(entry_ptr(c, blockIdx.x));
        const uint4* rec = keys_g + c * KSTR + KOFF + ((en >> 12) & 0xFFF);
        for (int r = warp; r < (int)(en & 0xFFF) * 3; r += 12) {
            uint4 v;
            for (int spins = 0;; spins++) {
                asm volatile("ld.volatile.global.v4.u32 {%0, %1, %2, %3}, [%4];" : "=r"(v.x), "=r"(v.y), "=r"(v.z), "=r"(v.w) : "l"(rec + r / 3) : "memory");
                if (__all_sync(~0u, (v.w & 0xC0C0C0u) == rtag)) break;
                if (spins > (1 << 22)) __trap();
            }
            const int j = r % 3;
            const uint32_t w = j == 0 ? v.x : (j == 1 ? v.y : v.z);
            const int dl = w >> 23, s = (w >> 7) & 0xFFFF;
            if (dl >= 384) continue;
            const uint2 ev = __ldg((const uint2*)e_attr + c * CQ * 4 + ((v.w >> (8 * j)) & 63) * 128 + (w & 127));
            const uint32_t xs = __ldg((const uint32_t*)(x + (size_t)s * 64) + lane);
            const uint32_t xd = __ldg((const uint32_t*)(x + (size_t)(node0 + dl) * 64) + lane);
            float g0 = 0.f, g1 = 0.f, h0 = 0.f, h1 = 0.f;
#pragma unroll 2
            for (int k = 0; k < 64; k++) {
                const uint32_t a = __shfl_sync(~0u, xs, k >> 1), b = __shfl_sync(~0u, xd, k >> 1);
                const float xsv = (k & 1) ? bf_hi(a) : bf_lo(a), xdv = (k & 1) ? bf_hi(b) : bf_lo(b);
                const uint32_t wa = __ldg((const uint32_t*)(g_w + k * 64 + f));
                const uint32_t wb = __ldg((const uint32_t*)(g_w + (64 + k) * 64 + f));
                const uint32_t wv = __ldg((const uint32_t*)(v_w + k * 64 + f));
                g0 = fmaf(xdv, bf_lo(wa), g0); g1 = fmaf(xdv, bf_hi(wa), g1);
                g0 = fmaf(xsv, bf_lo(wb), g0); g1 = fmaf(xsv, bf_hi(wb), g1);
                h0 = fmaf(xsv, bf_lo(wv), h0); h1 = fmaf(xsv, bf_hi(wv), h1);
            }
            const float e4[4] = {bf_lo(ev.x), bf_hi(ev.x), bf_lo(ev.y), bf_hi(ev.y)};
#pragma unroll
            for (int k = 0; k < 4; k++) {
                const uint32_t wc = __ldg((const uint32_t*)(g_w + (128 + k) * 64 + f));
                g0 = fmaf(e4[k], bf_lo(wc), g0); g1 = fmaf(e4[k], bf_hi(wc), g1);
            }
            h0 *= 0.25f; h1 *= 0.25f;
            atomicAdd(agg + dl * 64 + f, fmaf(h0, tanh_ap(0.5f * g0), h0));
            atomicAdd(agg + dl * 64 + f + 1, fmaf(h1, tanh_ap(0.5f * g1), h1));
        }
    }
    bar_sync(BAR_CONS, 384);
    for (int n = warp; n < nnodes; n += 12) {
        const uint32_t xs = __ldg((const uint32_t*)(x + (size_t)(node0 + n) * 64) + lane);
        float a = 0.f, b = 0.f;
#pragma unroll 2
        for (int k = 0; k < 64; k++) {
            const uint32_t t = __shfl_sync(~0u, xs, k >> 1);
            const float xv = (k & 1) ? bf_hi(t) : bf_lo(t);
            const uint32_t wu = __ldg((const uint32_t*)(u_w + k * 64 + f));
            a = fmaf(xv, bf_lo(wu), a); b = fmaf(xv, bf_hi(wu), b);
        }
        a = fmaf(a, 0.5f, agg[n * 64 + f]); b = fmaf(b, 0.5f, agg[n * 64 + f + 1]);
        ((uint32_t*)(out + (size_t)(node0 + n) * 64))[lane] = pack_bf2(fmaf(a, tanh_ap(a), a), fmaf(b, tanh_ap(b), b));
    }
}

__device__ __forceinline__ int plan_tiles(uint32_t sb, uint32_t tb, int p, int e, int e_end, int lane, const int (&v)[3], int p_own, int& t_own) {
    t_own = 1 << 20;
    int nt = 0, pw = p;
    bool forced = true;
    while (e < e_end) {
        const int ea = e & ~3, cnt = (e_end - ea + 63) >> 6;
        int f[3], pi[2], pn[2], pv[2];
#pragma unroll
        for (int j = 0; j < 3; j++) f[j] = (v[j] - ea + 63) >> 6;
        int kk[2];
        const bool mid = f[2] > 0 && f[2] < min(cnt, 64);
        const uint32_t b0 = __reduce_or_sync(~0u, mid && f[2] < 32 ? 1u << f[2] : 0), b1 = __reduce_or_sync(~0u, mid && f[2] >= 32 ? 1u << (f[2] - 32) : 0);
        const int below = __popc(__ballot_sync(~0u, f[2] <= 0));
        kk[0] = below + __popc(b0 << (31 - lane));
        kk[1] = below + __popc(b0) + __popc(b1 << (31 - lane));
        if (__popc(__ballot_sync(~0u, mid)) != __popc(b0) + __popc(b1)) {
#pragma unroll 1
            for (int i = 0; i < 32; i++) {
                const int c0 = __popc(__ballot_sync(~0u, f[2] <= i)), c1 = __popc(__ballot_sync(~0u, f[2] <= i + 32));
                if (lane == i) { kk[0] = c0; kk[1] = c1; }
            }
        }
#pragma unroll
        for (int h = 0; h < 2; h++) {
            const int k = kk[h];
            const int a = __shfl_sync(~0u, f[0], k & 31), b = __shfl_sync(~0u, f[1], k & 31);
            pi[h] = p_own - 32 + 3 * k + (a <= lane + 32 * h) + (b <= lane + 32 * h);
        }
        if (forced && lane == 0) pi[0] = p;
        const int both = pi[0] | pi[1] << 16;
        const int up = __shfl_sync(~0u, both, (lane + 31) & 31), dn = __shfl_sync(~0u, both, (lane + 1) & 31);
        pv[0] = lane ? up & 0xFFFF : pw; pv[1] = lane ? up >> 16 : up & 0xFFFF;
        pn[0] = lane < 31 ? dn & 0xFFFF : dn >> 16; pn[1] = dn >> 16;
        const int last = min(cnt, 63) - 1;
        const uint32_t v0 = __ballot_sync(~0u, pn[0] >= pi[0] + 4 || lane >= last), v1 = __ballot_sync(~0u, pn[1] >= pi[1] + 4 || lane + 32 >= last);
        const int first = v0 ? __ffs(v0) - 1 : 31 + __ffs(v1);
        pw = __reduce_max_sync(~0u, lane + 32 <= first ? pi[1] : (lane <= first ? pi[0] : 0));
        const int j4 = pw + 4 - (p_own - 31) - 3 * lane;
        const int cut = min(e_end, __reduce_min_sync(~0u, j4 <= 0 ? v[0] : (j4 == 1 ? v[1] : (j4 == 2 ? v[2] : e_end))));
#pragma unroll
        for (int h = 0; h < 2; h++) {
            const int i = lane + 32 * h;
            if (i <= first) {
                uint32_t mv = ((1u << (pi[h] - pv[h])) - 1) << (pv[h] & 3);
                mv |= mv >> 4;
                sts128(tb + (nt + i) * 16, make_uint4((ea + 64 * i) * 4, (min(64, cut - ea - 64 * i) << 8) | (i ? 0 : e & 3),
                                                      ((mv & 3) * 0x2000400u) & 0x4000400u, ((mv & 12) * 0x800100u) & 0x4000400u));
            }
        }
        t_own = min(t_own, nt + __reduce_min_sync(~0u, pi[0] >= p_own && lane <= first ? lane : (pi[1] >= p_own && lane + 32 <= first ? lane + 32 : 1 << 20)));
        forced = cut <= ea + 64 * (first + 1);
        e = min(cut, ea + 64 * (first + 1));
        p = pw + 4;
        nt += first + 1;
    }
    return nt;
}

__global__ void __launch_bounds__(NTHR, 1)
egc_kernel(const int* __restrict__ dst, const int* __restrict__ src, const __nv_bfloat16* __restrict__ e_attr,
           const __nv_bfloat16* __restrict__ x, uint4* keys_g, uint32_t* epoch_g, int mode,
           const __nv_bfloat16* __restrict__ u_w, const __nv_bfloat16* __restrict__ v_w, const __nv_bfloat16* __restrict__ g_w,
           __nv_bfloat16* out, const __grid_constant__ CUtensorMap tmx, const __grid_constant__ CUtensorMap tmg,
           const __grid_constant__ CUtensorMap tmv, const __grid_constant__ CUtensorMap tmu) {
    extern __shared__ __align__(1024) char smem[];
    const uint32_t sb = (uint32_t)__cvta_generic_to_shared(smem);
    const int tid = threadIdx.x, lane = tid & 31;
    const int warp = __shfl_sync(~0u, tid >> 5, 0);
    const int wg = warp >> 2, w4 = warp & 3;
    const int cta = blockIdx.x;
    const int node0 = cta * NB;
    const int nnodes = min(NB, kN - node0);
    const int q0 = cta * CQ, q1 = min(q0 + CQ, NQUAD);
    auto expect = [&](uint32_t bar, uint32_t bytes) {
        asm volatile("mbarrier.arrive.expect_tx.shared::cta.b64 _, [%0], %1;" ::"r"(bar), "r"(bytes) : "memory");
    };
    auto tile_load = [&](uint32_t bar, uint32_t to, const CUtensorMap* tm, int row) {
        asm volatile("cp.async.bulk.tensor.2d.shared::cluster.global.tile.mbarrier::complete_tx::bytes [%0], [%1, {%3, %4}], [%2];"
                     ::"r"(to), "l"(tm), "r"(bar), "r"(0), "r"(row) : "memory");
    };
    auto piece = [&](int i) {
        const uint32_t bar = sb + SM_LBAR + i * 8;
        if (i < 8) {
            const uint32_t bytes = i % 4 < 3 ? 6144 : (q1 - q0 - 1152) * 16;
            expect(bar, bytes);
            asm volatile("cp.async.bulk.shared::cluster.global.mbarrier::complete_tx::bytes [%0], [%1], %2, [%3];"
                         ::"r"(sb + SM_DST + i * 6144), "l"((const uint4*)(i < 4 ? dst : src) + q0 + (i % 4) * 384), "r"(bytes), "r"(bar) : "memory");
        } else {
            expect(bar, 8192);
            tile_load(bar, sb + xs_off(1 + (i & 1)) + ((i - 8) >> 1) * 8192, &tmx, node0 + 64 * (i - 8));
        }
    };
    uint32_t epoch = 0;
    if (warp == 13) epoch = ldg_cg(epoch_g);
    if (warp == 15 && elect_one()) {
#pragma unroll
        for (int i = 0; i < WIN; i++) mbar_init(sb + SM_LBAR + i * 8, 1);
        if (mode & 1) {
#pragma unroll
            for (int i = 0; i < WIN; i++) piece(i);
        }
#pragma unroll
        for (int i = WIN; i < 16; i++) mbar_init(sb + SM_LBAR + i * 8, 1);
    }
    if (tid < 104) sts128(sb + SM_CNT1 + tid * 16, make_uint4(0, 0, 0, 0));
    if (tid == 104) sts128(sb + SM_VAR, make_uint4(0, 0, 0, 0));
    if (warp == 4) sts128(sb + SM_XA + 192 * 256 + lane * 16, make_uint4(0, 0, 0, 0));
    if (warp >= 5 && warp < 8 && elect_one()) {
#pragma unroll
        for (int j = 0; j < 9; j++) mbar_init(sb + SM_BAR + (warp - 5) * 72 + j * 8, j < 3 ? 65 : (j < 6 || j == 8 ? 4 : 1));
        if (sb & 1023) __trap();
    }
    __syncwarp();

    if (wg == 3) {
        asm volatile("setmaxnreg.dec.sync.aligned.u32 56;");
        if (w4 == 3) bar_arrive(0, NTHR); else bar_sync(0, NTHR);

        if (w4 == 3) {
            auto load_w = [&]() {
                expect(sb + LB_W, 260 * 128);
                tile_load(sb + LB_W, sb + SM_XA + 25600, &tmu, 0);
                tile_load(sb + LB_W, sb + SM_XA, &tmg, 0);
                tile_load(sb + LB_W, sb + SM_XA + 17408, &tmv, 0);
            };
            if (elect_one()) {
                if (mode & 1) {
#pragma unroll
                    for (int i = WIN; i < 8 + XE; i++) {
                        if (i >= 8 && !(mode & 2)) break;
                        mbar_wait(sb + SM_LBAR + (i - WIN) * 8, 0);
                        piece(i);
                        if (i == 8) load_w();
                    }
                } else {
                    load_w();
#pragma unroll
                    for (int i = 8; i < 8 + XE; i++) piece(i);
                }
            }
            __syncwarp();
            if (!(mode & 2)) return;
            bar_sync(BAR_IN, 416);
            if (elect_one()) {
#pragma unroll
                for (int i = 8 + XE; i < 14; i++) piece(i);
            }
            __syncwarp();
            mbar_wait(sb + SM_LBAR + 13 * 8, 0);
            if (elect_one()) asm volatile("cp.async.bulk.prefetch.L2.global [%0], %1;" ::"l"((const uint4*)e_attr + 2 * (q0 + EE * 128)), "r"((q1 - q0 - EE * 128) * 32) : "memory");
            __syncwarp();
            const uint32_t key_ld = opaque(sb + SM_SK + lane * 4), row_st = opaque(sb + SM_AUX + 1024 + lane * 16);
            if (lds32(sb + SM_VAR) > CAPC) return;
            bar_sync(BAR_D, NTHR);
            uint32_t tbw[3];
            int ntw[3];
#pragma unroll
            for (int w = 0; w < 3; w++) { const uint2 v = lds64(sb + SM_VAR + 16 + w * 8); tbw[w] = v.x; ntw[w] = v.y; }
            const int ntm = max(ntw[0], max(ntw[1], ntw[2]));
            auto fetch_e = [&](uint32_t a, uint32_t k0, uint32_t k1) {
                asm volatile("{\n.reg .pred p, r;\n.reg .u32 t;\nand.b32 t, %4, 8;\nsetp.ne.u32 p, t, 0;\nand.b32 t, %5, 8;\nsetp.ne.u32 r, t, 0;\n"
                             "@p cp.async.ca.shared.global [%0], [%2], 8;\n@!p cp.async.cg.shared.global [%0], [%2], 16, 8;\n"
                             "@r cp.async.ca.shared.global [%1], [%3], 8;\n@!r cp.async.cg.shared.global [%1], [%3], 16, 8;\n}"
                             ::"r"(a), "r"(a + 512), "l"((const char*)e_attr + (k0 & 0x7FFFF8)), "l"((const char*)e_attr + (k1 & 0x7FFFF8)), "r"(k0), "r"(k1) : "memory");
            };
            uint32_t st = 0, ph = 1;
#pragma unroll 1
            for (int i = 0; i < ntm; i++) {
#pragma unroll
                for (int w = 0; w < 3; w++) {
                    if (i < ntw[w]) {
                        const uint32_t ka = key_ld + lds32(tbw[w] + i * 16);
                        const uint32_t k0 = lds32(ka), k1 = lds32(ka + 128);
                        mbar_wait(sb + SM_BAR + w * 72 + 24 + st * 8, ph);
                        fetch_e(row_st + (w * 3 + st) * 2048, k0, k1);
                        mbar_cp_arrive(sb + SM_BAR + w * 72 + st * 8);
                    }
                }
                if (++st == 3) { st = 0; ph ^= 1; }
            }
            asm volatile("cp.async.wait_all;" ::: "memory");
            return;
        }

        if (w4 == 1) {
            if (lane == 0) {
                sts128(sb + SM_VAR + 48, make_uint4((epoch % 127u + 1u) << 25, (epoch % 3u + 1u) * 0x404040u, (epoch + 1) % 381u, 0));
                mbar_arrive(sb + LB_TAG);
            }
            __syncwarp();
            if (lane == 1) asm volatile("prefetch.global.L2 [%0];" ::"l"(g_w + cta * 64));
            if (lane == 2 && cta < 128) asm volatile("prefetch.global.L2 [%0];" ::"l"((cta < 64 ? v_w : u_w) + (cta & 63) * 64));
            if (lane == 3) asm volatile("prefetch.tensormap [%0];" ::"l"(&tmx) : "memory");
            if (lane == 4) asm volatile("prefetch.tensormap [%0];" ::"l"(&tmg) : "memory");
            if (lane == 5) asm volatile("prefetch.tensormap [%0];" ::"l"(&tmv) : "memory");
            if (lane == 6) asm volatile("prefetch.tensormap [%0];" ::"l"(&tmu) : "memory");
        } else if (mode & 1) {
            if (w4 == 2) {
                bar_sync(BAR_R, 416);
                uint32_t c[5], s = 0;
#pragma unroll
                for (int j = 0; j < 5; j++) { c[j] = ((lds32(sb + SM_CNT1 + (lane * 5 + j) * 4) + 2) * 21846 >> 16) * 4; s += c[j]; }
                uint32_t inc = s;
#pragma unroll
                for (int o = 1; o < 32; o <<= 1) { uint32_t v = __shfl_up_sync(~0u, inc, o); if (lane >= o) inc += v; }
                uint32_t run = inc - s;
#pragma unroll
                for (int j = 0; j < 5; j++) { sts32(sb + SM_OFF1 + (lane * 5 + j) * 4, run); run += c[j]; }
                bar_arrive(BAR_S, 448);
            } else {
                mbar_wait(sb + LB_TAG, 0);
                const uint32_t tag = lds32(sb + SM_VAR + 48);
                bar_sync(BAR_S, 448);
                uint32_t en[5];
#pragma unroll
                for (int j = 0; j < 5; j++) {
                    const int b = min(lane + 32 * j, NCTA);
                    const uint32_t o0 = lds32(sb + SM_OFF1 + b * 4), o1 = lds32(sb + SM_OFF1 + b * 4 + 4);
                    en[j] = tag | (o0 << 10) | ((o1 - o0) >> 2);
                    if (lane + 32 * j < 136) asm volatile("st.relaxed.gpu.global.u32 [%0], %1;" ::"l"(entry_ptr(cta, lane + 32 * j)), "r"(en[j]) : "memory");
                    en[j] |= 1u << 24;
                }
                bar_sync(BAR_KEYS, 416);
                if (lds32(sb + SM_VAR + 48)) { const uint32_t t0 = clock(); while ((uint32_t)clock() - t0 < 400) {} }
#pragma unroll
                for (int j = 0; j < 5; j++)
                    if (lane + 32 * j < 136) asm volatile("st.relaxed.gpu.global.u32 [%0], %1;" ::"l"(entry_ptr(cta, lane + 32 * j)), "r"(en[j]) : "memory");
                if ((mode & 2) && lane == 0) asm volatile("cp.async.bulk.prefetch.L2.global [%0], %1;" ::"l"((const uint4*)e_attr + 2 * q0), "r"(EE * 4096) : "memory");
                __syncwarp();
            }
        }
        if (!(mode & 2)) return;

        const uint32_t bars = sb + SM_BAR + w4 * 72;
        const uint32_t r0 = lane >> 3, c0 = lane & 7;
        uint32_t xs0[4];
#pragma unroll
        for (int i = 0; i < 4; i++) xs0[i] = opaque(sb + w4 * 8192 + (4 * r0 + i) * 128 + ((c0 ^ ((4 * r0 + i) & 7)) << 4));
        uint64_t gbase = (uint64_t)x + c0 * 16;
        asm volatile("" : "+l"(gbase));
        const uint32_t src_ld = opaque(sb + SM_SS + r0 * 16), key_ld = opaque(sb + SM_SK + lane * 4);
        const uint32_t one = 0x3F80 + ((uint32_t)mode >> 8), two = 2 + ((uint32_t)mode >> 8);
        const int lane8 = opaque(lane << 8 | 255), lane8b = opaque((lane + 32) << 8 | 255);
        const uint32_t aux0 = sb + SM_AUX + w4 * 3 * 2048 + lane * 16;
        uint32_t tb;
        int nt, e1, va, vb, pv[3];
#pragma unroll 1
        for (uint32_t attempt = 1;; attempt++) {
            if (w4 == 2) {
                bar_sync(BAR_B, 416);
                uint4 u = lds128(sb + SM_CNT2 + lane * 32), v = lds128(sb + SM_CNT2 + lane * 32 + 16);
                u.y += u.x; u.z += u.y; u.w += u.z; v.x += u.w; v.y += v.x; v.z += v.y;
                const uint32_t s = v.w + v.z;
                uint32_t inc = s;
#pragma unroll
                for (int o = 1; o < 32; o <<= 1) { uint32_t t = __shfl_up_sync(~0u, inc, o); if (lane >= o) inc += t; }
                const uint32_t r = inc - s;
                sts128(sb + SM_PST + lane * 32, make_uint4(r, r + u.x, r + u.y, r + u.z));
                sts128(sb + SM_PST + lane * 32 + 16, make_uint4(r + u.w, r + v.x, r + v.y, r + v.z));
            }
            bar_sync(BAR_C, 480);
            const uint2 st = lds64(sb + SM_VAR);
            e1 = lds32(sb + SM_PST + 192 * 4);
            va = lds32(sb + SM_PST + (33 + lane) * 4); vb = lds32(sb + SM_PST + (97 + lane) * 4);
#pragma unroll
            for (int j = 0; j < 3; j++) pv[j] = lds32(sb + SM_PST + max(w4 * 64 - 31 + 3 * lane + j, 0) * 4);
            if (st.x > CAPC) return;
            if (st.y < attempt) break;
        }
        int p0 = 0, p1 = 192, e0 = 0;
        {
            const int ka = ((e1 + 63 + DYN) >> 6) / 3;
            const bool ia = va <= 64 * ka || lane == 0;
            const int pa = __reduce_max_sync(~0u, ia ? 33 + lane : 0), ea = __reduce_max_sync(~0u, ia ? va : 0);
            const int kb = ((e1 - ea + 63 + DYN / 2) >> 6) / 2;
            const bool ib = vb <= (ea & ~3) + 64 * kb || lane == 0;
            const int pb = __reduce_max_sync(~0u, ib ? 97 + lane : 0), eb = __reduce_max_sync(~0u, ib ? vb : 0);
            if (w4 == 0) { p1 = pa; e1 = ea; }
            else if (w4 == 1) { p0 = pa; e0 = ea; p1 = pb; e1 = eb; }
            else { p0 = pb; e0 = eb; }
        }
        tb = sb + SM_TBL + ((e0 >> 6) + (p0 >> 2) + 10 * w4) * 16;
        int t_own;
        nt = plan_tiles(sb, tb, p0, e0, e1, lane, pv, w4 * 64, t_own);
        const bool late = t_own > nt - 2;
        if (lane < 4) sts128(tb + (nt + lane) * 16, make_uint4((e0 & ~3) * 4, 0x80000000u, 0, 0));
        if (lane == 0) { sts64(sb + SM_VAR + 16 + w4 * 8, tb, nt); sts32(sb + SM_VAR + 64 + w4 * 4, p0 | p1 << 8 | late << 16); }
        if (w4 == 2) { put_record(sb + SM_SK + (e1 + lane) * 4, 0, 0); put_record(sb + SM_SK + (e1 + 32 + lane) * 4, 0, 0); }
        bar_sync(BAR_D, NTHR);
        uint32_t oh[3][2], sr[16], k0, k1;
#pragma unroll
        for (int j = 0; j < 3; j++) oh[j][0] = oh[j][1] = aux0;
        auto load_src = [&](uint32_t e8) {
#pragma unroll
            for (int j = 0; j < 4; j++) { const uint4 v = lds128(src_ld + e8 + 64 * j); sr[4 * j] = v.x; sr[4 * j + 1] = v.y; sr[4 * j + 2] = v.z; sr[4 * j + 3] = v.w; }
        };
        auto gather = [&](int stage, bool paced) {
#pragma unroll
            for (int j = 0; j < 16; j++) {
                cp16(xs0[j & 3] + xs_off(stage) + (j >> 2) * 2048, (const void*)(gbase + sr[j]));
                if (paced && j % PACE == PACE - 1) sched_fence();
            }
            mbar_cp_arrive(bars + stage * 8);
        };
        auto load_aux = [&](uint32_t e8) { k0 = lds32(key_ld + e8); k1 = lds32(key_ld + e8 + 128); };
        auto store_aux = [&](int stage, int n) {
            uint32_t n0, n1;
            asm volatile("{\n.reg .u32 t;\nand.b32 t, %1, 7;\nmad.lo.u32 %0, t, %3, %2;\n}" : "=r"(n0) : "r"(k0), "r"(aux0), "r"(two));
            asm volatile("{\n.reg .u32 t;\nand.b32 t, %1, 7;\nmad.lo.u32 %0, t, %3, %2;\n}" : "=r"(n1) : "r"(k1), "r"(aux0), "r"(two));
            asm volatile("{\n.reg .pred p, r;\n.reg .b16 o, z;\nsetp.ge.s32 p, %8, %9;\nsetp.lt.and.s32 p, %4, %5, p;\nsetp.lt.s32 r, %6, %5;\nmov.b32 {o, z}, %7;\n"
                         "st.shared.u16 [%0], 0;\nst.shared.u16 [%1], 0;\n@p st.shared.u16 [%2], o;\n@r st.shared.u16 [%3], o;\n}"
                         ::"r"(oh[stage][0] + stage * 2048), "r"(oh[stage][1] + stage * 2048 + 512), "r"(n0 + stage * 2048), "r"(n1 + stage * 2048 + 512),
                           "r"(lane8), "r"(n), "r"(lane8b), "r"(one), "r"(lane), "r"(n & 3) : "memory");
            oh[stage][0] = n0; oh[stage][1] = n1;
            fence_async();
            __syncwarp();
            mbar_arrive_if(bars + stage * 8, lane == 0);
        };
        auto extra = [&](int j, int stage) {
            if (elect_one()) {
                expect(bars + 48 + j * 8, 8192);
                tile_load(bars + 48 + j * 8, sb + xs_off(stage) + w4 * 8192, &tmx, node0 + w4 * 128 + j * 64);
            }
            __syncwarp();
        };
        uint2 en1 = lds64(tb + 16);
        {
            const uint2 en0 = lds64(tb);
            load_src(en0.x);
            load_aux(en0.x);
            if (nt > 0) gather(0, false); else { fence_async(); extra(0, 0); }
            store_aux(0, en0.y);
            load_src(en1.x);
            if (2 * w4 + 2 > XE) bar_sync(BAR_G + w4, 160);
            if (nt > 1) gather(1, false); else extra(1 - nt, 1);
        }
        uint32_t ph = 1;
        int left = nt;
        uint2 en2 = lds64(tb + 32);
        auto step = [&](auto stage_c) {
            constexpr int S = decltype(stage_c)::value, S1 = (S + 1) % 3, S2 = (S + 2) % 3;
            load_aux(en1.x);
            load_src(en2.x);
            const uint2 en3 = lds64(tb + (S + 3) * 16);
            mbar_wait(bars + 24 + S2 * 8, S == 0 ? ph : ph ^ 1);
            store_aux(S1, en1.y);
            if (left - S > 2) gather(S2, true); else extra(2 - (left - S), S2);
            en1 = en2; en2 = en3;
        };
#pragma unroll 1
        while (left > 0) {
            step(IC<0>());
            if (left == 1) break;
            step(IC<1>());
            if (left == 2) break;
            step(IC<2>());
            left -= 3; tb += 48; ph ^= 1;
        }
        if (!late && lane < 4) mbar_arrive(bars + 64);
        asm volatile("cp.async.wait_all;" ::: "memory");
    } else {
        asm volatile("setmaxnreg.inc.sync.aligned.u32 152;");
        const int g = lane >> 2, q = lane & 3;
        const int f0 = 16 * w4 + 2 * g;
        bar_sync(0, NTHR);
        mbar_wait(sb + LB_TAG, 0);
        const uint32_t tag = lds32(sb + SM_VAR + 48), rtag = lds32(sb + SM_VAR + 52);
        const uint4 pad = make_uint4((384u + 2 * lane) << 23, (448u + 2 * lane) << 23, (385u + 2 * lane) << 23, rtag | cta << 24);
        if (mode & 1) {
#pragma unroll
            for (int i = 0; i < 6; i++) {
                const int c = tid + 384 * i;
                if (c < OUTC) sts128(sb + SM_SK + c * 16, c < OUTC * 3 / 4 ? make_uint4(pad.x, pad.y, pad.z, pad.y ^ (32u << 23)) : make_uint4(pad.w, pad.w, pad.w, pad.w));
            }
            const bool ok3 = q0 + tid + 384 * 3 < q1;
            uint4 rd[4], rs[4];
            uint32_t w[16], bin4[16], aw[16], ab[16];
#pragma unroll
            for (int i = 0; i < 4; i++) {
                mbar_wait(sb + LB_DST + i * 8, 0);
                rd[i] = lds128(sb + SM_DST + (tid + 384 * i) * 16);
                if (i == 3 && !ok3) rd[3] = make_uint4(0, 0, 0, 0);
                const uint32_t d4[4] = {rd[i].x, rd[i].y, rd[i].z, rd[i].w};
#pragma unroll
                for (int j = 0; j < 4; j++) {
                    const uint32_t b = d4[j] / NB;
                    bin4[4 * i + j] = b * 4;
                    aw[4 * i + j] = 0;
                    if (i < 3 || ok3) aw[4 * i + j] = atoms_add(sb + SM_CNT1 + b * 4, 1);
                    w[4 * i + j] = d4[j] - b * NB;
                }
            }
            bar_arrive(BAR_R, 416);
#pragma unroll
            for (int i = 0; i < 16; i++) {
                w[i] = (w[i] << 23) | (lane * 4 + (i & 3));
                ab[i] = sb + SM_OH + aw[i] + (aw[i] * 21846 >> 16);
                aw[i] = sb + SM_SK + aw[i] * 4;
            }
            bar_sync(BAR_S, 448);
#pragma unroll
            for (int i = 0; i < 16; i++) { const uint32_t o = lds32(sb + SM_OFF1 + bin4[i]); aw[i] += 3 * o; ab[i] += o; }
#pragma unroll
            for (int i = 0; i < 4; i++) {
                if (i < 3 || ok3) {
#pragma unroll
                    for (int j = 0; j < 4; j++) asm volatile("st.shared.u8 [%0], %1;" ::"r"(ab[4 * i + j]), "r"(rtag | (warp + 12 * i)) : "memory");
                }
            }
#pragma unroll
            for (int i = 0; i < 16; i++) asm volatile("" : "+r"(aw[i]), "+r"(w[i]));
#pragma unroll
            for (int i = 0; i < 4; i++) mbar_wait(sb + LB_SRC + i * 8, 0);
#pragma unroll
            for (int i = 0; i < 4; i++) rs[i] = lds128(sb + SM_SRC + (tid + 384 * i) * 16);
#pragma unroll
            for (int i = 0; i < 4; i++) {
                if (i < 3 || ok3) {
                    const uint32_t s4[4] = {rs[i].x, rs[i].y, rs[i].z, rs[i].w};
#pragma unroll
                    for (int j = 0; j < 4; j++) sts32(aw[4 * i + j], w[4 * i + j] + s4[j] * 128);
                }
            }
            bar_sync(BAR_CONS, 384);
            uint4 ch[6];
#pragma unroll
            for (int i = 0; i < 6; i++) {
                const uint32_t c = min(tid + 384 * i, OUTC - 1);
                ch[i] = make_uint4(lds32(sb + SM_SK + c * 12), lds32(sb + SM_SK + c * 12 + 4), lds32(sb + SM_SK + c * 12 + 8), lds32(sb + SM_OH + c * 4));
            }
#pragma unroll
            for (int i = 0; i < 6; i++) {
                if (i < 5 || tid < OUTC - 1920)
                    asm volatile("st.relaxed.gpu.global.v4.u32 [%0], {%1, %2, %3, %4};" ::"l"(keys_g + cta * KSTR + KOFF + tid + 384 * i), "r"(ch[i].x), "r"(ch[i].y), "r"(ch[i].z), "r"(ch[i].w) : "memory");
            }
            bar_arrive(BAR_KEYS, 416);
            if (!(mode & 2)) return;
        }
        const uint32_t* pe = entry_ptr(warp * 11 + min(lane, 10), cta);
        uint32_t en = ld_relaxed(pe);
#pragma unroll
        for (int i = 0; i < 6; i++) sts128(sb + SM_KS + (tid + 384 * i) * 16, pad);
#pragma unroll
        for (int j = 0; j < 3; j++) sts128(sb + SM_AUX + tid * 16 + j * 6144, make_uint4(0, 0, 0, 0));
        uint32_t wa[16], wb[16], wv[16], wc0 = 0, wc1 = 0;
        {
            mbar_wait(sb + LB_W, 0);
            const uint32_t a = sb + SM_XA + 2 * q * 128 + ((f0 * 2) ^ (q << 5)), b = (a ^ 16) + 128;
#pragma unroll
            for (int i = 0; i < 16; i++) {
                wa[i] = lds32((i & 1 ? b : a) + (i >> 1) * 1024);
                wb[i] = lds32((i & 1 ? b : a) + 8192 + (i >> 1) * 1024);
                wv[i] = lds32((i & 1 ? b : a) + 17408 + (i >> 1) * 1024);
            }
            if (q < 2) { wc0 = lds32(a + 16384); wc1 = lds32(b + 16384); }
            if (wg == 2) {
                uint32_t wu[16];
#pragma unroll
                for (int i = 0; i < 16; i++) wu[i] = lds32((i & 1 ? b : a) + 25600 + (i >> 1) * 1024);
                cvt_wfrag(wu, 0x3F003F00u);
#pragma unroll
                for (int i = 0; i < 4; i++) sts128(sb + SM_U + i * 2048 + (tid & 127) * 16, make_uint4(wu[4 * i], wu[4 * i + 1], wu[4 * i + 2], wu[4 * i + 3]));
            }
            cvt_wfrag(wa, 0x3F003F00u);
            cvt_wfrag(wb, 0x3F003F00u);
            cvt_wfrag(wv, 0x3E803E80u);
            const uint32_t r0 = wc0, r1 = wc1;
            wc0 = scale_bf2(__byte_perm(r0, r1, 0x5410), 0x3F003F00u);
            wc1 = scale_bf2(__byte_perm(r0, r1, 0x7632), 0x3F003F00u);
#pragma unroll
            for (int i = 0; i < 16; i++) asm volatile("" : "+r"(wa[i]), "+r"(wb[i]), "+r"(wv[i]));
            sched_fence();
            bar_sync(BAR_CONS, 384);
            sts64(sb + SM_XA + (wg * 64 + q) * 256 + ((w4 * 64 + g * 8) ^ (q << 5)), 0, 0);
        }
        const uint32_t xa_off = sb + SM_XA + (wg * 64 + q) * 256 + ((w4 * 64 + g * 8) ^ (q << 5));
        auto gemm_xa = [&]() {
            mbar_wait(sb + LB_OWN + wg * 16, 0);
            mbar_wait(sb + LB_OWN + wg * 16 + 8, 0);
            float da[32], db[32];
            const uint64_t dx = mkdesc(sb + wg * 8192, 16, 1024, 1);
            wg_fence();
            wg_k64<0>(da, wa, dx + xs_off(1) / 16);
            wg_commit();
            wg_k64<0>(db, wa, dx + xs_off(2) / 16);
            wg_commit();
            uint32_t mx = 0;
            auto put = [&](float (&d)[32], uint32_t a) {
#pragma unroll
                for (int j = 0; j < 8; j++) {
                    const uint32_t u = pack_bf2(d[4 * j], d[4 * j + 1]), v = pack_bf2(d[4 * j + 2], d[4 * j + 3]);
                    sts64(a + j * 1024, u, v);
                    asm("max.xorsign.abs.bf16x2 %0, %0, %1;" : "+r"(mx) : "r"(u));
                    asm("max.xorsign.abs.bf16x2 %0, %0, %1;" : "+r"(mx) : "r"(v));
                }
            };
            wg_wait<1>();
            fence_regs(da);
            put(da, xa_off);
            wg_wait<0>();
            fence_regs(db);
            put(db, xa_off + 8192);
            if (((mx & 0x7FFF7FFFu) + 0x3D803D80u) & 0x80008000u) sts32(sb + SM_VAR + 8, 1);
        };
        const bool early = 2 * wg + 2 <= XE;
        uint32_t myoff;
        {
#pragma unroll 1
            for (int spins = 0; !__all_sync(~0u, (en & 0xFE000000u) == tag); spins++) {
                en = ld_relaxed(pe);
                if (spins > (1 << 22)) __trap();
            }
            uint32_t sent = ld_relaxed(pe);
            if (lane > 10) en = 0;
            const uint32_t len = en & 0xFFF;
            uint32_t inc = len;
#pragma unroll
            for (int o = 1; o < 16; o <<= 1) { uint32_t v = __shfl_up_sync(~0u, inc, o); if (lane >= o) inc += v; }
            uint32_t base = 0;
            if (lane == 15) base = atoms_add(sb + SM_VAR, inc);
            myoff = __shfl_sync(~0u, base, 15) + inc - len;
            if (__any_sync(~0u, lane < 16 && myoff + len > CAPC)) en = 0;
            const uint32_t l8 = lane & 7;
            const bool big = __any_sync(~0u, (en & 0xFFF) > 25);
            const uint4* pk[3];
            uint32_t sk[3], c[3], l[3];
#pragma unroll
            for (int r = 0; r < 3; r++) {
                const int run = 4 * r + (lane >> 3);
                const uint32_t e = __shfl_sync(~0u, en, run), of = __shfl_sync(~0u, myoff, run);
                const uint32_t st = (e >> 12) & 0xFFF;
                l[r] = e & 0xFFF; c[r] = l8 - (st & 7);
                pk[r] = keys_g + (warp * 11 + run) * KSTR + KOFF + (st & ~7u) + l8;
                sk[r] = sb + SM_KS + (of + c[r]) * 16;
                asm volatile("" : "+l"(pk[r]), "+r"(sk[r]), "+r"(l[r]), "+r"(c[r]));
            }
#pragma unroll 1
            for (int spins = 0; !__all_sync(~0u, sent & (1u << 24)); spins++) {
                sent = ld_relaxed(pe);
                if (spins > (1 << 22)) __trap();
            }
            asm volatile("fence.acquire.gpu;" ::: "memory");
#pragma unroll
            for (int r = 0; r < 3; r++) {
#pragma unroll
                for (int j = 0; j < 4; j++) cp16p(sk[r] + j * 128, pk[r] + 8 * j, c[r] + 8 * j < l[r]);
            }
            if (big) {
#pragma unroll
                for (int r = 0; r < 3; r++) {
#pragma unroll 1
                    for (uint32_t j = 32; j + c[r] < l[r]; j += 8) cp16(sk[r] + j * 16, pk[r] + j);
                }
            }
            if (early) gemm_xa();
        }
        {
            uint32_t key[18], row[18], rk[18], pa[18];
            uint32_t hd[6] = {};
            bool six;
            auto unpack = [&](int i) {
                const uint32_t base = (hd[i] >> 24) * (CQ * 32);
#pragma unroll
                for (int j = 0; j < 3; j++) {
                    const uint32_t v = row[3 * i + j];
                    key[3 * i + j] = (base + __byte_perm(hd[i], 0, 0x4440 + j) * 1024 + (v & 127) * 8) | ((v >> 23) & 7);
                    row[3 * i + j] = v & 0x7FFF80;
                    asm volatile("" : "+r"(key[3 * i + j]), "+r"(row[3 * i + j]));
                }
            };
#pragma unroll 1
            for (uint32_t attempt = 1;; attempt++) {
                asm volatile("cp.async.wait_all;" ::: "memory");
                if (attempt == 1) bar_sync(BAR_IN, 416); else bar_sync(BAR_CONS, 384);
                const uint32_t nchunk = lds32(sb + SM_VAR);
                const bool slow = nchunk > CAPC;
                six = warp * 32 + 1920 < nchunk;
                uint4 k4[6];
#pragma unroll
                for (int i = 0; i < 6; i++) k4[i] = lds128(sb + SM_KS + (tid + 384 * i) * 16);
                uint32_t stale = 0;
#pragma unroll
                for (int i = 0; i < 6; i++) {
                    row[3 * i] = k4[i].x; row[3 * i + 1] = k4[i].y; row[3 * i + 2] = k4[i].z;
#pragma unroll
                    for (int j = 3 * i; j < 3 * i + 3; j++) {
                        pa[j] = sb + SM_CNT2 + (row[j] >> 24) * 4;
                        if (i < 5 || six) rk[j] = atoms_add(pa[j], 1);
                    }
                    hd[i] = k4[i].w ^ rtag;
                    stale |= hd[i];
                }
                if (stale & 0xC0C0C0u) sts32(sb + SM_VAR + 4, attempt);
                bar_arrive(BAR_B, 416);
#pragma unroll
                for (int i = 0; i < UNP; i++) unpack(i);
                if (cta == 0 && tid == 0 && mode == 3) *epoch_g = lds32(sb + SM_VAR + 56);
                bar_sync(BAR_C, 480);
                if (slow) {
                    mbar_wait(sb + LB_OWN + wg * 16, 0);
                    mbar_wait(sb + LB_OWN + wg * 16 + 8, 0);
                    bar_sync(BAR_CONS, 384);
                    slow_path(smem, keys_g, x, e_attr, u_w, v_w, g_w, out);
                    return;
                }
                if (lds32(sb + SM_VAR + 4) < attempt) break;
                if (tid < 64) sts128(sb + SM_CNT2 + tid * 16, make_uint4(0, 0, 0, 0));
                if (attempt > (1 << 20)) __trap();
#pragma unroll 1
                for (int run = 0; run < 11; run++) {
                    const uint32_t e = __shfl_sync(~0u, en, run), of = __shfl_sync(~0u, myoff, run);
#pragma unroll 1
                    for (uint32_t j = lane; j < (e & 0xFFF); j += 32)
                        cp16(sb + SM_KS + (of + j) * 16, keys_g + (warp * 11 + run) * KSTR + KOFF + ((e >> 12) & 0xFFF) + j);
                }
            }
#pragma unroll
            for (int i = 0; i < 15; i++) pa[i] = lds32(pa[i] + (SM_PST - SM_CNT2));
#pragma unroll
            for (int i = 0; i < 15; i++) {
                if (i % 3 == 0 && i / 3 >= UNP) unpack(i / 3);
                put_record(sb + SM_SK + (rk[i] + pa[i]) * 4, key[i], row[i]);
            }
            if (six) {
                unpack(5);
#pragma unroll
                for (int i = 15; i < 18; i++) rk[i] += lds32(pa[i] + (SM_PST - SM_CNT2));
#pragma unroll
                for (int i = 15; i < 18; i++) put_record(sb + SM_SK + rk[i] * 4, key[i], row[i]);
            }
        }
        const uint32_t bars = sb + SM_BAR + wg * 72;
        const uint64_t dx0 = mkdesc(sb + wg * 8192, 16, 1024, 1);
        uint64_t dSm = mkdesc(sb + SM_AUX + wg * 3 * 2048 - 16, 128, 128, 0);
        constexpr uint64_t S2A = (uint64_t)((1024 - 128) >> 4) << 16;
        const uint64_t zero = (uint32_t)mode >> 8;
        const bool lane0 = lane == 0;
        bar_sync(BAR_D, NTHR);
        if (!early) { gemm_xa(); bar_arrive(BAR_G + wg, 160); }

        const uint2 tbn = lds64(sb + SM_VAR + 16 + wg * 8);
        uint32_t tb = opaque(tbn.x + 8 + q * 2);
        const int nt = __shfl_sync(~0u, tbn.y, 0);
        const uint32_t rng = lds32(sb + SM_VAR + 64 + wg * 4);
        uint32_t a_cur = opaque(xa_off + ((rng & 255) + ((q - rng) & 3) - wg * 64 - q) * 256);
        uint2 xa = lds64(a_cur);
        float d2[4] = {0.f, 0.f, 0.f, 0.f};
        uint32_t m[16];
#pragma unroll
        for (int i = 0; i < 16; i++) m[i] = 0;
        uint32_t ph = 0, dlt = 0;
        bool ready = false;
        int left = nt;
        auto tile = [&](auto stage_c) {
            constexpr int S = decltype(stage_c)::value, S2 = (S + 2) % 3;
            float ga[32], ha[32];
            if (!ready) mbar_wait(bars + S * 8, ph);
            wg_fence();
            wg_seg(d2, m, dSm + 1 + S2 * 128);
            wg_n64<0>(ga, xa.x, xa.y, wc0, wc1, dSm + 1 + S2A + S * 128);
            wg_k64<1>(ga, wb, dx0 + xs_off(S) / 16);
            wg_commit();
            wg_k64<0>(ha, wv, dx0 + xs_off(S) / 16);
            wg_commit();
            sched_fence();
            const uint32_t dn = lds16(tb + (S + 1) * 16);
            wg_wait<1>();
            fence_regs(ga);
#pragma unroll
            for (int i = 0; i < NPRE; i++) ga[i] = tanh_v(ga[i]);
            fence_regs(d2);
            asm volatile("{\n.reg .pred p;\n.reg .b32 u, v;\n"
                         "setp.ne.u32 p, %5, 0;\n"
                         "cvt.rn.bf16x2.f32 u, %1, %0;\n"
                         "cvt.rn.bf16x2.f32 v, %3, %2;\n"
                         "@p st.shared.v2.u32 [%4+-1024], {u, v};\n"
                         "@p mov.b32 %0, 0;\n@p mov.b32 %1, 0;\n@p mov.b32 %2, 0;\n@p mov.b32 %3, 0;\n}"
                         : "+f"(d2[0]), "+f"(d2[1]), "+f"(d2[2]), "+f"(d2[3]) : "r"(a_cur), "r"(dlt) : "memory");
            a_cur += dn;
            dlt = dn;
            xa = lds64(a_cur);
            sched_fence();
            wg_wait<0>();
            fence_regs(ha);
            __syncwarp();
            mbar_arrive_if(bars + 24 + S * 8, lane0);
#pragma unroll
            for (int i = 0; i < 16; i++) {
                if (i == 14) {
                    uint32_t r;
                    asm volatile("{\n.reg .pred p;\nmbarrier.test_wait.parity.shared::cta.b64 p, [%1], %2;\nselp.u32 %0, 1, 0, p;\n}"
                                 : "=r"(r) : "r"(bars + ((S + 1) % 3) * 8), "r"(S == 2 ? ph ^ 1 : ph) : "memory");
                    ready = r != 0;
                }
                if (2 * i + NPRE < 32) ga[2 * i + NPRE] = tanh_v(ga[2 * i + NPRE]);
                if (2 * i + 1 + NPRE < 32) ga[2 * i + 1 + NPRE] = tanh_v(ga[2 * i + 1 + NPRE]);
                m[i] = pack_v(fmaf(ha[2 * i], ga[2 * i], ha[2 * i]), fmaf(ha[2 * i + 1], ga[2 * i + 1], ha[2 * i + 1]));
            }
        };
#pragma unroll 1
        while (left > 0) {
            tile(IC<0>());
            if (left == 1) break;
            tile(IC<1>());
            if (left == 2) break;
            tile(IC<2>());
            left -= 3; tb += 48; ph ^= 1;
            dSm += zero;
        }
        const uint32_t s0 = nt % 3, s1 = s0 == 2 ? 0 : s0 + 1, s2 = s0 == 0 ? 2 : s0 - 1;
        float y0[32], y1[32];
        auto load_agg = [&](float (&y)[32], uint32_t a) {
#pragma unroll
            for (int j = 0; j < 8; j++) {
                const uint2 v = lds64(a + j * 1024);
                y[4 * j] = bf_lo(v.x); y[4 * j + 1] = bf_hi(v.x); y[4 * j + 2] = bf_lo(v.y); y[4 * j + 3] = bf_hi(v.y);
            }
            fence_regs(y);
        };
        auto finish = [&](float (&y)[32], uint32_t* po, int nrem) {
#pragma unroll
            for (int j = 0; j < 8; j++) {
                const float a = y[4 * j], b = y[4 * j + 1], c = y[4 * j + 2], d = y[4 * j + 3];
                const uint32_t o0 = pack_bf2(fmaf(a, tanh_ap(a), a), fmaf(c, tanh_ap(c), c)), o1 = pack_bf2(fmaf(b, tanh_ap(b), b), fmaf(d, tanh_ap(d), d));
                if (8 * j < nrem) { po[256 * j] = o0; po[256 * j + 32] = o1; }
            }
        };
        const uint32_t rend = lds32(sb + SM_VAR + 64 + wg * 4) >> 8;
        const uint32_t a_end = xa_off + ((rend & 255) - wg * 64 - q) * 256;
#pragma unroll 1
        for (uint32_t a = a_cur + 1024; a < a_end; a += 1024) sts64(a, 0, 0);
        if (__any_sync(~0u, a_cur < xa_off + 8192)) {
            fence_async();
            wg_fence();
            wg_seg(d2, m, dSm + 1 + s2 * 128);
            wg_commit();
            wg_wait<0>();
            fence_regs(d2);
            if (a_cur < a_end) sts64(a_cur, pack_bf2(d2[0], d2[1]), pack_bf2(d2[2], d2[3]));
            a_cur = ~0u;
        }
        mbar_wait(bars + 48, 0);
        mbar_wait(bars + 56, 0);
        uint32_t wu[16];
#pragma unroll
        for (int i = 0; i < 4; i++) {
            const uint4 v = lds128(sb + SM_U + i * 2048 + (tid & 127) * 16);
            wu[4 * i] = v.x; wu[4 * i + 1] = v.y; wu[4 * i + 2] = v.z; wu[4 * i + 3] = v.w;
        }
        load_agg(y0, xa_off);
#pragma unroll
        for (int i = 0; i < 16; i++) asm volatile("" : "+r"(wu[i]), "+r"(m[i]) :: "memory");
        fence_regs(d2);
        sched_fence();
        wg_fence();
        wg_seg(d2, m, dSm + 1 + s2 * 128);
        wg_k64<1>(y0, wu, dx0 + xs_off(s0) / 16);
        wg_commit();
        wg_wait<0>();
        fence_regs(d2);
        fence_regs(y0);
        asm volatile("{\n.reg .pred p;\nsetp.lt.u32 p, %0, %3;\n@p st.shared.v2.u32 [%0], {%1, %2};\n}"
                     ::"r"(a_cur), "r"(pack_bf2(d2[0], d2[1])), "r"(pack_bf2(d2[2], d2[3])), "r"(a_end) : "memory");
        __syncwarp();
        mbar_arrive_if(bars + 64, lane0 && rend >= 256);
        if (wg < 2) mbar_wait(bars + 72 + 64, 0);
        load_agg(y1, xa_off + 8192);
        wg_fence();
        wg_k64<1>(y1, wu, dx0 + xs_off(s1) / 16);
        wg_commit();
        uint32_t* po = (uint32_t*)(out + (size_t)(node0 + wg * 128 + 2 * q) * 64 + f0);
        const int nrem = nnodes - wg * 128 - 2 * q;
        sched_fence();
        finish(y0, po, nrem);
        sched_fence();
        wg_wait<0>();
        fence_regs(y1);
        finish(y1, po + 2048, nrem - 64);
        bar_sync(BAR_CONS, 384);
        if (lds32(sb + SM_VAR + 8)) slow_path(smem, keys_g, x, e_attr, u_w, v_w, g_w, out);
    }
}

__global__ void bump_epoch() { g_epoch = (g_epoch + 1u) % 381u; }

}

extern "C" void kernel_launch(void* const* d_in, const int* in_sizes, int n_in, void* d_out, int out_size) {
    const __nv_bfloat16* x = (const __nv_bfloat16*)d_in[0];
    const __nv_bfloat16* e_attr = (const __nv_bfloat16*)d_in[1];
    const int* src = (const int*)d_in[2];
    const int* dst = (const int*)d_in[3];
    const __nv_bfloat16* u_w = (const __nv_bfloat16*)d_in[4];
    const __nv_bfloat16* v_w = (const __nv_bfloat16*)d_in[5];
    const __nv_bfloat16* g_w = (const __nv_bfloat16*)d_in[6];
    __nv_bfloat16* out = (__nv_bfloat16*)d_out;
    static int fused = -1;
    static CUtensorMap tm[4];
    static const void* tm_ptr[4] = {nullptr, nullptr, nullptr, nullptr};
    const void* want[4] = {x, g_w, v_w, u_w};
    const cuuint32_t rows[4] = {kN, 132, 64, 64}, box_rows[4] = {64, 132, 64, 64};
    for (int i = 0; i < 4; i++) {
        if (tm_ptr[i] == want[i]) continue;
        typedef CUresult (*EncodeFn)(CUtensorMap*, CUtensorMapDataType, cuuint32_t, void*, const cuuint64_t*, const cuuint64_t*,
                                     const cuuint32_t*, const cuuint32_t*, CUtensorMapInterleave, CUtensorMapSwizzle,
                                     CUtensorMapL2promotion, CUtensorMapFloatOOBfill);
        void* fn = nullptr;
        cudaDriverEntryPointQueryResult qr;
        cudaGetDriverEntryPoint("cuTensorMapEncodeTiled", &fn, cudaEnableDefault, &qr);
        const cuuint64_t dims[2] = {64, rows[i]}, strides[1] = {128};
        const cuuint32_t box[2] = {64, box_rows[i]}, es[2] = {1, 1};
        ((EncodeFn)fn)(&tm[i], CU_TENSOR_MAP_DATA_TYPE_BFLOAT16, 2, (void*)want[i], dims, strides, box, es, CU_TENSOR_MAP_INTERLEAVE_NONE,
                       CU_TENSOR_MAP_SWIZZLE_128B, CU_TENSOR_MAP_L2_PROMOTION_NONE, CU_TENSOR_MAP_FLOAT_OOB_FILL_NONE);
        tm_ptr[i] = want[i];
    }
    static uint4* keys_g;
    static uint32_t* epoch_g;
    if (fused < 0) {
        cudaGetSymbolAddress((void**)&keys_g, g_keys);
        cudaGetSymbolAddress((void**)&epoch_g, g_epoch);
        int dev = 0, sms = 0, occ = 0, coop = 0;
        cudaGetDevice(&dev);
        cudaDeviceGetAttribute(&sms, cudaDevAttrMultiProcessorCount, dev);
        cudaFuncSetAttribute(egc_kernel, cudaFuncAttributeMaxDynamicSharedMemorySize, SMEM_BYTES);
        cudaOccupancyMaxActiveBlocksPerMultiprocessor(&occ, egc_kernel, NTHR, SMEM_BYTES);
        cudaDeviceGetAttribute(&coop, cudaDevAttrCooperativeLaunch, dev);
        fused = (coop && sms * occ >= NCTA) ? 1 : 0;
    }
    if (fused) {
        int mode = 3;
        void* args[] = {&dst, &src, &e_attr, &x, &keys_g, &epoch_g, &mode, &u_w, &v_w, &g_w, &out, &tm[0], &tm[1], &tm[2], &tm[3]};
        cudaLaunchCooperativeKernel((const void*)egc_kernel, dim3(NCTA), dim3(NTHR), args, SMEM_BYTES, cudaStreamPerThread);
    } else {
        egc_kernel<<<NCTA, NTHR, SMEM_BYTES>>>(dst, src, e_attr, x, keys_g, epoch_g, 1, u_w, v_w, g_w, out, tm[0], tm[1], tm[2], tm[3]);
        egc_kernel<<<NCTA, NTHR, SMEM_BYTES>>>(dst, src, e_attr, x, keys_g, epoch_g, 2, u_w, v_w, g_w, out, tm[0], tm[1], tm[2], tm[3]);
        bump_epoch<<<1, 1>>>();
    }
}
```
